```python
import torch

def _softmax(x, axis=-1):
    return torch.softmax(x, dim=axis)
def _gelu(x):
    return torch.nn.functional.gelu(x, approximate="tanh")
def _silu(x):
    return torch.nn.functional.silu(x)
def _sigmoid(x):
    return torch.sigmoid(x)
def _layernorm(x, axis=-1, eps=1e-5):
    m = x.mean(dim=axis, keepdim=True)
    v = x.var(dim=axis, keepdim=True, unbiased=False)
    return (x - m) / torch.sqrt(v + eps)
def _scatter_add(tgt, idx, src, axis=0):
    return tgt.clone().index_add_(axis, idx, src)
def _segment_sum(src, seg, n):
    out = torch.zeros((n,) + src.shape[1:], dtype=src.dtype)
    return out.index_add_(0, seg, src)
def _pad(x, pw):
    flat = tuple(v for pair in reversed(pw) for v in pair)
    return torch.nn.functional.pad(x, flat)

kernel_name = 'standalone__glu_gated_swiglu__prompt'

def setup_inputs():

    _w = (lambda a: (lambda t: t.to(torch.bfloat16) if t.is_floating_point() else t)(torch.as_tensor(a)))
    B, S, D, F = 1, 2048, 448, 1792
    return {
        "x": _w((lambda *s: torch.randn(*s, dtype=torch.bfloat16) * 0.05)(B, S, D)),
        "w1": _w((lambda *s: torch.randn(*s, dtype=torch.bfloat16) * 0.05)(D, F) * (2.0 / D) ** 0.5),
        "w3": _w((lambda *s: torch.randn(*s, dtype=torch.bfloat16) * 0.05)(D, F) * (2.0 / D) ** 0.5),
        "w2": _w((lambda *s: torch.randn(*s, dtype=torch.bfloat16) * 0.05)(F, D) * (2.0 / F) ** 0.5),
    }

def reference(x, w1, w3, w2):
    gate = torch.einsum("bsd,df->bsf", x, w1)
    up = torch.einsum("bsd,df->bsf", x, w3)
    h = _silu(gate) * up
    out = torch.einsum("bsf,fd->bsd", h, w2)
    return out
```

```cpp
#include <cuda_runtime.h>
#include <cuda_bf16.h>
#include <cuda.h>
#include <stdint.h>

__device__ __forceinline__ void wgmma_ss_n128(float (&d)[64], uint32_t abase, uint32_t aoff, uint32_t ahi,
        uint32_t bbase, uint32_t boff, uint32_t bhi, bool accumulate) {
    if (accumulate) {
        asm volatile("{ .reg .b32 la, lb; .reg .b64 da, db;\n"
            "add.u32 la, %64, %65; mov.b64 da, {la, %66}; add.u32 lb, %67, %68; mov.b64 db, {lb, %69};\n"
            "wgmma.mma_async.sync.aligned.m64n128k16.f32.bf16.bf16 {%0, %1, %2, %3, %4, %5, %6, %7, %8, %9, %10, %11, %12, %13, %14, %15, %16, %17, %18, %19, %20, %21, %22, %23, %24, %25, %26, %27, %28, %29, %30, %31, %32, %33, %34, %35, %36, %37, %38, %39, %40, %41, %42, %43, %44, %45, %46, %47, %48, %49, %50, %51, %52, %53, %54, %55, %56, %57, %58, %59, %60, %61, %62, %63}, da, db, 1, 1, 1, 0, 1; }\n"
            :
            "+f"(d[0]), "+f"(d[1]), "+f"(d[2]), "+f"(d[3]), "+f"(d[4]), "+f"(d[5]), "+f"(d[6]), "+f"(d[7]),
            "+f"(d[8]), "+f"(d[9]), "+f"(d[10]), "+f"(d[11]), "+f"(d[12]), "+f"(d[13]), "+f"(d[14]), "+f"(d[15]),
            "+f"(d[16]), "+f"(d[17]), "+f"(d[18]), "+f"(d[19]), "+f"(d[20]), "+f"(d[21]), "+f"(d[22]), "+f"(d[23]),
            "+f"(d[24]), "+f"(d[25]), "+f"(d[26]), "+f"(d[27]), "+f"(d[28]), "+f"(d[29]), "+f"(d[30]), "+f"(d[31]),
            "+f"(d[32]), "+f"(d[33]), "+f"(d[34]), "+f"(d[35]), "+f"(d[36]), "+f"(d[37]), "+f"(d[38]), "+f"(d[39]),
            "+f"(d[40]), "+f"(d[41]), "+f"(d[42]), "+f"(d[43]), "+f"(d[44]), "+f"(d[45]), "+f"(d[46]), "+f"(d[47]),
            "+f"(d[48]), "+f"(d[49]), "+f"(d[50]), "+f"(d[51]), "+f"(d[52]), "+f"(d[53]), "+f"(d[54]), "+f"(d[55]),
            "+f"(d[56]), "+f"(d[57]), "+f"(d[58]), "+f"(d[59]), "+f"(d[60]), "+f"(d[61]), "+f"(d[62]), "+f"(d[63])
            : "r"(abase), "r"(aoff), "r"(ahi), "r"(bbase), "r"(boff), "r"(bhi));
    } else {
        asm volatile("{ .reg .b32 la, lb; .reg .b64 da, db;\n"
            "add.u32 la, %64, %65; mov.b64 da, {la, %66}; add.u32 lb, %67, %68; mov.b64 db, {lb, %69};\n"
            "wgmma.mma_async.sync.aligned.m64n128k16.f32.bf16.bf16 {%0, %1, %2, %3, %4, %5, %6, %7, %8, %9, %10, %11, %12, %13, %14, %15, %16, %17, %18, %19, %20, %21, %22, %23, %24, %25, %26, %27, %28, %29, %30, %31, %32, %33, %34, %35, %36, %37, %38, %39, %40, %41, %42, %43, %44, %45, %46, %47, %48, %49, %50, %51, %52, %53, %54, %55, %56, %57, %58, %59, %60, %61, %62, %63}, da, db, 0, 1, 1, 0, 1; }\n"
            :
            "=f"(d[0]), "=f"(d[1]), "=f"(d[2]), "=f"(d[3]), "=f"(d[4]), "=f"(d[5]), "=f"(d[6]), "=f"(d[7]),
            "=f"(d[8]), "=f"(d[9]), "=f"(d[10]), "=f"(d[11]), "=f"(d[12]), "=f"(d[13]), "=f"(d[14]), "=f"(d[15]),
            "=f"(d[16]), "=f"(d[17]), "=f"(d[18]), "=f"(d[19]), "=f"(d[20]), "=f"(d[21]), "=f"(d[22]), "=f"(d[23]),
            "=f"(d[24]), "=f"(d[25]), "=f"(d[26]), "=f"(d[27]), "=f"(d[28]), "=f"(d[29]), "=f"(d[30]), "=f"(d[31]),
            "=f"(d[32]), "=f"(d[33]), "=f"(d[34]), "=f"(d[35]), "=f"(d[36]), "=f"(d[37]), "=f"(d[38]), "=f"(d[39]),
            "=f"(d[40]), "=f"(d[41]), "=f"(d[42]), "=f"(d[43]), "=f"(d[44]), "=f"(d[45]), "=f"(d[46]), "=f"(d[47]),
            "=f"(d[48]), "=f"(d[49]), "=f"(d[50]), "=f"(d[51]), "=f"(d[52]), "=f"(d[53]), "=f"(d[54]), "=f"(d[55]),
            "=f"(d[56]), "=f"(d[57]), "=f"(d[58]), "=f"(d[59]), "=f"(d[60]), "=f"(d[61]), "=f"(d[62]), "=f"(d[63])
            : "r"(abase), "r"(aoff), "r"(ahi), "r"(bbase), "r"(boff), "r"(bhi));
    }
}
__device__ __forceinline__ void wgmma_ss_n64(float (&d)[32], uint32_t abase, uint32_t aoff, uint32_t ahi,
        uint32_t bbase, uint32_t boff, uint32_t bhi, bool accumulate) {
    if (accumulate) {
        asm volatile("{ .reg .b32 la, lb; .reg .b64 da, db;\n"
            "add.u32 la, %32, %33; mov.b64 da, {la, %34}; add.u32 lb, %35, %36; mov.b64 db, {lb, %37};\n"
            "wgmma.mma_async.sync.aligned.m64n64k16.f32.bf16.bf16 {%0, %1, %2, %3, %4, %5, %6, %7, %8, %9, %10, %11, %12, %13, %14, %15, %16, %17, %18, %19, %20, %21, %22, %23, %24, %25, %26, %27, %28, %29, %30, %31}, da, db, 1, 1, 1, 0, 1; }\n"
            :
            "+f"(d[0]), "+f"(d[1]), "+f"(d[2]), "+f"(d[3]), "+f"(d[4]), "+f"(d[5]), "+f"(d[6]), "+f"(d[7]),
            "+f"(d[8]), "+f"(d[9]), "+f"(d[10]), "+f"(d[11]), "+f"(d[12]), "+f"(d[13]), "+f"(d[14]), "+f"(d[15]),
            "+f"(d[16]), "+f"(d[17]), "+f"(d[18]), "+f"(d[19]), "+f"(d[20]), "+f"(d[21]), "+f"(d[22]), "+f"(d[23]),
            "+f"(d[24]), "+f"(d[25]), "+f"(d[26]), "+f"(d[27]), "+f"(d[28]), "+f"(d[29]), "+f"(d[30]), "+f"(d[31])
            : "r"(abase), "r"(aoff), "r"(ahi), "r"(bbase), "r"(boff), "r"(bhi));
    } else {
        asm volatile("{ .reg .b32 la, lb; .reg .b64 da, db;\n"
            "add.u32 la, %32, %33; mov.b64 da, {la, %34}; add.u32 lb, %35, %36; mov.b64 db, {lb, %37};\n"
            "wgmma.mma_async.sync.aligned.m64n64k16.f32.bf16.bf16 {%0, %1, %2, %3, %4, %5, %6, %7, %8, %9, %10, %11, %12, %13, %14, %15, %16, %17, %18, %19, %20, %21, %22, %23, %24, %25, %26, %27, %28, %29, %30, %31}, da, db, 0, 1, 1, 0, 1; }\n"
            :
            "=f"(d[0]), "=f"(d[1]), "=f"(d[2]), "=f"(d[3]), "=f"(d[4]), "=f"(d[5]), "=f"(d[6]), "=f"(d[7]),
            "=f"(d[8]), "=f"(d[9]), "=f"(d[10]), "=f"(d[11]), "=f"(d[12]), "=f"(d[13]), "=f"(d[14]), "=f"(d[15]),
            "=f"(d[16]), "=f"(d[17]), "=f"(d[18]), "=f"(d[19]), "=f"(d[20]), "=f"(d[21]), "=f"(d[22]), "=f"(d[23]),
            "=f"(d[24]), "=f"(d[25]), "=f"(d[26]), "=f"(d[27]), "=f"(d[28]), "=f"(d[29]), "=f"(d[30]), "=f"(d[31])
            : "r"(abase), "r"(aoff), "r"(ahi), "r"(bbase), "r"(boff), "r"(bhi));
    }
}
__device__ __forceinline__ void wgmma_rs_n128(float (&d)[64], uint32_t a0, uint32_t a1, uint32_t a2, uint32_t a3,
        uint32_t bbase, uint32_t boff, uint32_t bhi, bool accumulate) {
    if (accumulate) {
        asm volatile("{ .reg .b32 lb; .reg .b64 db;\n"
            "add.u32 lb, %68, %69; mov.b64 db, {lb, %70};\n"
            "wgmma.mma_async.sync.aligned.m64n128k16.f32.bf16.bf16 {%0, %1, %2, %3, %4, %5, %6, %7, %8, %9, %10, %11, %12, %13, %14, %15, %16, %17, %18, %19, %20, %21, %22, %23, %24, %25, %26, %27, %28, %29, %30, %31, %32, %33, %34, %35, %36, %37, %38, %39, %40, %41, %42, %43, %44, %45, %46, %47, %48, %49, %50, %51, %52, %53, %54, %55, %56, %57, %58, %59, %60, %61, %62, %63}, {%64, %65, %66, %67}, db, 1, 1, 1, 1; }\n"
            :
            "+f"(d[0]), "+f"(d[1]), "+f"(d[2]), "+f"(d[3]), "+f"(d[4]), "+f"(d[5]), "+f"(d[6]), "+f"(d[7]),
            "+f"(d[8]), "+f"(d[9]), "+f"(d[10]), "+f"(d[11]), "+f"(d[12]), "+f"(d[13]), "+f"(d[14]), "+f"(d[15]),
            "+f"(d[16]), "+f"(d[17]), "+f"(d[18]), "+f"(d[19]), "+f"(d[20]), "+f"(d[21]), "+f"(d[22]), "+f"(d[23]),
            "+f"(d[24]), "+f"(d[25]), "+f"(d[26]), "+f"(d[27]), "+f"(d[28]), "+f"(d[29]), "+f"(d[30]), "+f"(d[31]),
            "+f"(d[32]), "+f"(d[33]), "+f"(d[34]), "+f"(d[35]), "+f"(d[36]), "+f"(d[37]), "+f"(d[38]), "+f"(d[39]),
            "+f"(d[40]), "+f"(d[41]), "+f"(d[42]), "+f"(d[43]), "+f"(d[44]), "+f"(d[45]), "+f"(d[46]), "+f"(d[47]),
            "+f"(d[48]), "+f"(d[49]), "+f"(d[50]), "+f"(d[51]), "+f"(d[52]), "+f"(d[53]), "+f"(d[54]), "+f"(d[55]),
            "+f"(d[56]), "+f"(d[57]), "+f"(d[58]), "+f"(d[59]), "+f"(d[60]), "+f"(d[61]), "+f"(d[62]), "+f"(d[63])
            : "r"(a0), "r"(a1), "r"(a2), "r"(a3), "r"(bbase), "r"(boff), "r"(bhi));
    } else {
        asm volatile("{ .reg .b32 lb; .reg .b64 db;\n"
            "add.u32 lb, %68, %69; mov.b64 db, {lb, %70};\n"
            "wgmma.mma_async.sync.aligned.m64n128k16.f32.bf16.bf16 {%0, %1, %2, %3, %4, %5, %6, %7, %8, %9, %10, %11, %12, %13, %14, %15, %16, %17, %18, %19, %20, %21, %22, %23, %24, %25, %26, %27, %28, %29, %30, %31, %32, %33, %34, %35, %36, %37, %38, %39, %40, %41, %42, %43, %44, %45, %46, %47, %48, %49, %50, %51, %52, %53, %54, %55, %56, %57, %58, %59, %60, %61, %62, %63}, {%64, %65, %66, %67}, db, 0, 1, 1, 1; }\n"
            :
            "=f"(d[0]), "=f"(d[1]), "=f"(d[2]), "=f"(d[3]), "=f"(d[4]), "=f"(d[5]), "=f"(d[6]), "=f"(d[7]),
            "=f"(d[8]), "=f"(d[9]), "=f"(d[10]), "=f"(d[11]), "=f"(d[12]), "=f"(d[13]), "=f"(d[14]), "=f"(d[15]),
            "=f"(d[16]), "=f"(d[17]), "=f"(d[18]), "=f"(d[19]), "=f"(d[20]), "=f"(d[21]), "=f"(d[22]), "=f"(d[23]),
            "=f"(d[24]), "=f"(d[25]), "=f"(d[26]), "=f"(d[27]), "=f"(d[28]), "=f"(d[29]), "=f"(d[30]), "=f"(d[31]),
            "=f"(d[32]), "=f"(d[33]), "=f"(d[34]), "=f"(d[35]), "=f"(d[36]), "=f"(d[37]), "=f"(d[38]), "=f"(d[39]),
            "=f"(d[40]), "=f"(d[41]), "=f"(d[42]), "=f"(d[43]), "=f"(d[44]), "=f"(d[45]), "=f"(d[46]), "=f"(d[47]),
            "=f"(d[48]), "=f"(d[49]), "=f"(d[50]), "=f"(d[51]), "=f"(d[52]), "=f"(d[53]), "=f"(d[54]), "=f"(d[55]),
            "=f"(d[56]), "=f"(d[57]), "=f"(d[58]), "=f"(d[59]), "=f"(d[60]), "=f"(d[61]), "=f"(d[62]), "=f"(d[63])
            : "r"(a0), "r"(a1), "r"(a2), "r"(a3), "r"(bbase), "r"(boff), "r"(bhi));
    }
}
__device__ __forceinline__ void wgmma_rs_n64(float (&d)[32], uint32_t a0, uint32_t a1, uint32_t a2, uint32_t a3,
        uint32_t bbase, uint32_t boff, uint32_t bhi, bool accumulate) {
    if (accumulate) {
        asm volatile("{ .reg .b32 lb; .reg .b64 db;\n"
            "add.u32 lb, %36, %37; mov.b64 db, {lb, %38};\n"
            "wgmma.mma_async.sync.aligned.m64n64k16.f32.bf16.bf16 {%0, %1, %2, %3, %4, %5, %6, %7, %8, %9, %10, %11, %12, %13, %14, %15, %16, %17, %18, %19, %20, %21, %22, %23, %24, %25, %26, %27, %28, %29, %30, %31}, {%32, %33, %34, %35}, db, 1, 1, 1, 1; }\n"
            :
            "+f"(d[0]), "+f"(d[1]), "+f"(d[2]), "+f"(d[3]), "+f"(d[4]), "+f"(d[5]), "+f"(d[6]), "+f"(d[7]),
            "+f"(d[8]), "+f"(d[9]), "+f"(d[10]), "+f"(d[11]), "+f"(d[12]), "+f"(d[13]), "+f"(d[14]), "+f"(d[15]),
            "+f"(d[16]), "+f"(d[17]), "+f"(d[18]), "+f"(d[19]), "+f"(d[20]), "+f"(d[21]), "+f"(d[22]), "+f"(d[23]),
            "+f"(d[24]), "+f"(d[25]), "+f"(d[26]), "+f"(d[27]), "+f"(d[28]), "+f"(d[29]), "+f"(d[30]), "+f"(d[31])
            : "r"(a0), "r"(a1), "r"(a2), "r"(a3), "r"(bbase), "r"(boff), "r"(bhi));
    } else {
        asm volatile("{ .reg .b32 lb; .reg .b64 db;\n"
            "add.u32 lb, %36, %37; mov.b64 db, {lb, %38};\n"
            "wgmma.mma_async.sync.aligned.m64n64k16.f32.bf16.bf16 {%0, %1, %2, %3, %4, %5, %6, %7, %8, %9, %10, %11, %12, %13, %14, %15, %16, %17, %18, %19, %20, %21, %22, %23, %24, %25, %26, %27, %28, %29, %30, %31}, {%32, %33, %34, %35}, db, 0, 1, 1, 1; }\n"
            :
            "=f"(d[0]), "=f"(d[1]), "=f"(d[2]), "=f"(d[3]), "=f"(d[4]), "=f"(d[5]), "=f"(d[6]), "=f"(d[7]),
            "=f"(d[8]), "=f"(d[9]), "=f"(d[10]), "=f"(d[11]), "=f"(d[12]), "=f"(d[13]), "=f"(d[14]), "=f"(d[15]),
            "=f"(d[16]), "=f"(d[17]), "=f"(d[18]), "=f"(d[19]), "=f"(d[20]), "=f"(d[21]), "=f"(d[22]), "=f"(d[23]),
            "=f"(d[24]), "=f"(d[25]), "=f"(d[26]), "=f"(d[27]), "=f"(d[28]), "=f"(d[29]), "=f"(d[30]), "=f"(d[31])
            : "r"(a0), "r"(a1), "r"(a2), "r"(a3), "r"(bbase), "r"(boff), "r"(bhi));
    }
}
__device__ __forceinline__ void wgmma_rs_n32(float (&d)[16], uint32_t a0, uint32_t a1, uint32_t a2, uint32_t a3,
        uint32_t bbase, uint32_t boff, uint32_t bhi, bool accumulate) {
    if (accumulate) {
        asm volatile("{ .reg .b32 lb; .reg .b64 db;\n"
            "add.u32 lb, %20, %21; mov.b64 db, {lb, %22};\n"
            "wgmma.mma_async.sync.aligned.m64n32k16.f32.bf16.bf16 {%0, %1, %2, %3, %4, %5, %6, %7, %8, %9, %10, %11, %12, %13, %14, %15}, {%16, %17, %18, %19}, db, 1, 1, 1, 1; }\n"
            :
            "+f"(d[0]), "+f"(d[1]), "+f"(d[2]), "+f"(d[3]), "+f"(d[4]), "+f"(d[5]), "+f"(d[6]), "+f"(d[7]),
            "+f"(d[8]), "+f"(d[9]), "+f"(d[10]), "+f"(d[11]), "+f"(d[12]), "+f"(d[13]), "+f"(d[14]), "+f"(d[15])
            : "r"(a0), "r"(a1), "r"(a2), "r"(a3), "r"(bbase), "r"(boff), "r"(bhi));
    } else {
        asm volatile("{ .reg .b32 lb; .reg .b64 db;\n"
            "add.u32 lb, %20, %21; mov.b64 db, {lb, %22};\n"
            "wgmma.mma_async.sync.aligned.m64n32k16.f32.bf16.bf16 {%0, %1, %2, %3, %4, %5, %6, %7, %8, %9, %10, %11, %12, %13, %14, %15}, {%16, %17, %18, %19}, db, 0, 1, 1, 1; }\n"
            :
            "=f"(d[0]), "=f"(d[1]), "=f"(d[2]), "=f"(d[3]), "=f"(d[4]), "=f"(d[5]), "=f"(d[6]), "=f"(d[7]),
            "=f"(d[8]), "=f"(d[9]), "=f"(d[10]), "=f"(d[11]), "=f"(d[12]), "=f"(d[13]), "=f"(d[14]), "=f"(d[15])
            : "r"(a0), "r"(a1), "r"(a2), "r"(a3), "r"(bbase), "r"(boff), "r"(bhi));
    }
}

constexpr uint32_t POLL_LIMIT = 1u << 16;
__device__ __forceinline__ uint32_t recv_check3(const uint4* src, uint32_t* v, uint32_t tagHi) {
    uint32_t cnt;
    asm volatile("{ .reg .pred p; .reg .b32 t, u; .reg .b64 l, h; .reg .b128 q;\n"
        "mov.u32 %12, 0;\n"
        "CHK:\n"
        "xor.b32 t, %3, %14;\n"
        "xor.b32 u, %7, %14; or.b32 t, t, u;\n"
        "xor.b32 u, %11, %14; or.b32 t, t, u;\n"
        "setp.lt.u32 p, t, 65536; vote.sync.all.pred p, p, 0xffffffff; @p bra.uni DONE;\n"
        "add.u32 %12, %12, 1; setp.gt.u32 p, %12, %15; @p bra.uni DONE;\n"
        "ld.relaxed.gpu.global.b128 q, [%13+0]; mov.b128 {l, h}, q; mov.b64 {%0, %1}, l; mov.b64 {%2, %3}, h;\n"
        "ld.relaxed.gpu.global.b128 q, [%13+4096]; mov.b128 {l, h}, q; mov.b64 {%4, %5}, l; mov.b64 {%6, %7}, h;\n"
        "ld.relaxed.gpu.global.b128 q, [%13+8192]; mov.b128 {l, h}, q; mov.b64 {%8, %9}, l; mov.b64 {%10, %11}, h;\n"
        "bra.uni CHK;\n"
        "DONE: }\n"
        : "+r"(v[0]), "+r"(v[1]), "+r"(v[2]), "+r"(v[3]), "+r"(v[4]), "+r"(v[5]), "+r"(v[6]), "+r"(v[7]), "+r"(v[8]), "+r"(v[9]), "+r"(v[10]), "+r"(v[11]), "=r"(cnt)
        : "l"(src), "r"(tagHi), "n"(POLL_LIMIT) : "memory");
    return cnt;
}

__device__ __forceinline__ uint32_t recv_check5(const uint4* src, uint32_t* v, uint32_t tagHi) {
    uint32_t cnt;
    asm volatile("{ .reg .pred p; .reg .b32 t, u; .reg .b64 l, h; .reg .b128 q;\n"
        "mov.u32 %20, 0;\n"
        "CHK:\n"
        "xor.b32 t, %3, %22;\n"
        "xor.b32 u, %7, %22; or.b32 t, t, u;\n"
        "xor.b32 u, %11, %22; or.b32 t, t, u;\n"
        "xor.b32 u, %15, %22; or.b32 t, t, u;\n"
        "xor.b32 u, %19, %22; or.b32 t, t, u;\n"
        "setp.lt.u32 p, t, 65536; vote.sync.all.pred p, p, 0xffffffff; @p bra.uni DONE;\n"
        "add.u32 %20, %20, 1; setp.gt.u32 p, %20, %23; @p bra.uni DONE;\n"
        "ld.relaxed.gpu.global.b128 q, [%21+0]; mov.b128 {l, h}, q; mov.b64 {%0, %1}, l; mov.b64 {%2, %3}, h;\n"
        "ld.relaxed.gpu.global.b128 q, [%21+4096]; mov.b128 {l, h}, q; mov.b64 {%4, %5}, l; mov.b64 {%6, %7}, h;\n"
        "ld.relaxed.gpu.global.b128 q, [%21+8192]; mov.b128 {l, h}, q; mov.b64 {%8, %9}, l; mov.b64 {%10, %11}, h;\n"
        "ld.relaxed.gpu.global.b128 q, [%21+12288]; mov.b128 {l, h}, q; mov.b64 {%12, %13}, l; mov.b64 {%14, %15}, h;\n"
        "ld.relaxed.gpu.global.b128 q, [%21+16384]; mov.b128 {l, h}, q; mov.b64 {%16, %17}, l; mov.b64 {%18, %19}, h;\n"
        "bra.uni CHK;\n"
        "DONE: }\n"
        : "+r"(v[0]), "+r"(v[1]), "+r"(v[2]), "+r"(v[3]), "+r"(v[4]), "+r"(v[5]), "+r"(v[6]), "+r"(v[7]), "+r"(v[8]), "+r"(v[9]), "+r"(v[10]), "+r"(v[11]), "+r"(v[12]), "+r"(v[13]), "+r"(v[14]), "+r"(v[15]), "+r"(v[16]), "+r"(v[17]), "+r"(v[18]), "+r"(v[19]), "=r"(cnt)
        : "l"(src), "r"(tagHi), "n"(POLL_LIMIT) : "memory");
    return cnt;
}

__device__ __forceinline__ uint32_t recv_check8(const uint4* src, uint32_t* v, uint32_t tagHi) {
    uint32_t cnt;
    asm volatile("{ .reg .pred p; .reg .b32 t, u; .reg .b64 l, h; .reg .b128 q;\n"
        "mov.u32 %32, 0;\n"
        "CHK:\n"
        "xor.b32 t, %3, %34;\n"
        "xor.b32 u, %7, %34; or.b32 t, t, u;\n"
        "xor.b32 u, %11, %34; or.b32 t, t, u;\n"
        "xor.b32 u, %15, %34; or.b32 t, t, u;\n"
        "xor.b32 u, %19, %34; or.b32 t, t, u;\n"
        "xor.b32 u, %23, %34; or.b32 t, t, u;\n"
        "xor.b32 u, %27, %34; or.b32 t, t, u;\n"
        "xor.b32 u, %31, %34; or.b32 t, t, u;\n"
        "setp.lt.u32 p, t, 65536; vote.sync.all.pred p, p, 0xffffffff; @p bra.uni DONE;\n"
        "add.u32 %32, %32, 1; setp.gt.u32 p, %32, %35; @p bra.uni DONE;\n"
        "ld.relaxed.gpu.global.b128 q, [%33+0]; mov.b128 {l, h}, q; mov.b64 {%0, %1}, l; mov.b64 {%2, %3}, h;\n"
        "ld.relaxed.gpu.global.b128 q, [%33+4096]; mov.b128 {l, h}, q; mov.b64 {%4, %5}, l; mov.b64 {%6, %7}, h;\n"
        "ld.relaxed.gpu.global.b128 q, [%33+8192]; mov.b128 {l, h}, q; mov.b64 {%8, %9}, l; mov.b64 {%10, %11}, h;\n"
        "ld.relaxed.gpu.global.b128 q, [%33+12288]; mov.b128 {l, h}, q; mov.b64 {%12, %13}, l; mov.b64 {%14, %15}, h;\n"
        "ld.relaxed.gpu.global.b128 q, [%33+16384]; mov.b128 {l, h}, q; mov.b64 {%16, %17}, l; mov.b64 {%18, %19}, h;\n"
        "ld.relaxed.gpu.global.b128 q, [%33+20480]; mov.b128 {l, h}, q; mov.b64 {%20, %21}, l; mov.b64 {%22, %23}, h;\n"
        "ld.relaxed.gpu.global.b128 q, [%33+24576]; mov.b128 {l, h}, q; mov.b64 {%24, %25}, l; mov.b64 {%26, %27}, h;\n"
        "ld.relaxed.gpu.global.b128 q, [%33+28672]; mov.b128 {l, h}, q; mov.b64 {%28, %29}, l; mov.b64 {%30, %31}, h;\n"
        "bra.uni CHK;\n"
        "DONE: }\n"
        : "+r"(v[0]), "+r"(v[1]), "+r"(v[2]), "+r"(v[3]), "+r"(v[4]), "+r"(v[5]), "+r"(v[6]), "+r"(v[7]), "+r"(v[8]), "+r"(v[9]), "+r"(v[10]), "+r"(v[11]), "+r"(v[12]), "+r"(v[13]), "+r"(v[14]), "+r"(v[15]), "+r"(v[16]), "+r"(v[17]), "+r"(v[18]), "+r"(v[19]), "+r"(v[20]), "+r"(v[21]), "+r"(v[22]), "+r"(v[23]), "+r"(v[24]), "+r"(v[25]), "+r"(v[26]), "+r"(v[27]), "+r"(v[28]), "+r"(v[29]), "+r"(v[30]), "+r"(v[31]), "=r"(cnt)
        : "l"(src), "r"(tagHi), "n"(POLL_LIMIT) : "memory");
    return cnt;
}

constexpr int M_TOK = 2048, D_MODEL = 448, F_FF = 1792;
constexpr int BM = 128;
constexpr int BF = 224;
constexpr int SLOT = 16384;
constexpr int NSLOT = 14;
constexpr int SMEM_BYTES = NSLOT * SLOT + 384 + 1024;
constexpr int NTHREADS = 384;
constexpr int K32 = 4, K64 = 3, KS = 5;
constexpr int NLOCAL = 3;
constexpr uint32_t SPIN_LIMIT = 1u << 17;

__device__ uint4 g_hbox[128 * 16 * 256];
__device__ uint32_t g_epoch[128];
__device__ uint32_t g_zcnt[16 * 32];

__device__ __forceinline__ uint32_t smem_u32(const void* p) { return (uint32_t)__cvta_generic_to_shared(p); }
__device__ __forceinline__ void mbar_init(uint32_t bar, uint32_t cnt) { asm volatile("mbarrier.init.shared::cta.b64 [%0], %1;" :: "r"(bar), "r"(cnt) : "memory"); }
__device__ __forceinline__ void mbar_expect_tx(uint32_t bar, uint32_t bytes) { asm volatile("mbarrier.arrive.expect_tx.shared::cta.b64 _, [%0], %1;" :: "r"(bar), "r"(bytes) : "memory"); }
__device__ __forceinline__ void mbar_arrive_cluster(uint32_t cluster_addr) { asm volatile("mbarrier.arrive.shared::cluster.b64 _, [%0];" :: "r"(cluster_addr) : "memory"); }
__device__ __forceinline__ void mbar_wait(uint32_t bar, uint32_t parity) {
    asm volatile("{ .reg .pred p; .reg .b32 n; mov.u32 n, 0;\n"
                 "WAIT: mbarrier.try_wait.parity.shared::cta.b64 p, [%0], %1; @p bra DONE;\n"
                 "add.u32 n, n, 1; setp.lt.u32 p, n, %2; @p bra WAIT;\n"
                 "DONE: }\n" :: "r"(bar), "r"(parity), "n"(SPIN_LIMIT) : "memory");
}
__device__ __forceinline__ void tma2d(uint32_t dst, const CUtensorMap* m, int c0, int c1, uint32_t bar) {
    asm volatile("cp.async.bulk.tensor.2d.shared::cluster.global.mbarrier::complete_tx::bytes [%0], [%1, {%3, %4}], [%2];"
        :: "r"(dst), "l"((uint64_t)m), "r"(bar), "r"(c0), "r"(c1) : "memory");
}
__device__ __forceinline__ void tma2d_mc(uint32_t dst, const CUtensorMap* m, int c0, int c1, uint32_t bar) {
    asm volatile("cp.async.bulk.tensor.2d.shared::cluster.global.mbarrier::complete_tx::bytes.multicast::cluster [%0], [%1, {%3, %4}], [%2], %5;"
        :: "r"(dst), "l"((uint64_t)m), "r"(bar), "r"(c0), "r"(c1), "h"((uint16_t)3) : "memory");
}
__device__ __forceinline__ void prefetch_tmap(const CUtensorMap* m) { asm volatile("prefetch.tensormap [%0];" :: "l"((uint64_t)m) : "memory"); }
__device__ __forceinline__ bool elect_one() {
    uint32_t pred;
    asm volatile("{ .reg .pred p; elect.sync _|p, 0xffffffff; selp.u32 %0, 1, 0, p; }" : "=r"(pred));
    return pred;
}
__device__ __forceinline__ void wg_fence() { asm volatile("wgmma.fence.sync.aligned;" ::: "memory"); }
__device__ __forceinline__ void wg_commit() { asm volatile("wgmma.commit_group.sync.aligned;" ::: "memory"); }
template <int N> __device__ __forceinline__ void wg_wait() { asm volatile("wgmma.wait_group.sync.aligned %0;" :: "n"(N) : "memory"); }
template <int N> __device__ __forceinline__ void pin(float (&d)[N]) {
#pragma unroll
    for (int i = 0; i < N; i++) asm volatile("" : "+f"(d[i]) :: "memory");
}
__host__ __device__ constexpr uint32_t dlo(uint32_t byte_off, uint32_t lbo) { return (byte_off >> 4) + ((lbo >> 4) << 16); }
constexpr uint32_t HI128 = (1024 >> 4) | (1u << 30);
constexpr uint32_t HI64 = (512 >> 4) | (2u << 30);
__device__ __forceinline__ uint32_t prmt(uint32_t a, uint32_t b, uint32_t sel) { uint32_t r; asm("prmt.b32 %0, %1, %2, %3;" : "=r"(r) : "r"(a), "r"(b), "r"(sel)); return r; }
__device__ __forceinline__ uint32_t pack_bf16(float lo, float hi) { uint32_t r; asm("cvt.rn.bf16x2.f32 %0, %1, %2;" : "=r"(r) : "f"(hi), "f"(lo)); return r; }
__device__ __forceinline__ float swiglu(float g, float u) {
    float e, r;
    asm("ex2.approx.ftz.f32 %0, %1;" : "=f"(e) : "f"(g * -1.4426950408889634f));
    asm("rcp.approx.ftz.f32 %0, %1;" : "=f"(r) : "f"(1.0f + e));
    return (g * r) * u;
}
__device__ __forceinline__ uint32_t swiglu2(float g0, float u0, float g1, float u1) { return pack_bf16(swiglu(g0, u0), swiglu(g1, u1)); }
__device__ __forceinline__ void st_pkt(uint4* p, uint32_t a, uint32_t b, uint32_t c, uint32_t d) {
    asm volatile("{ .reg .b64 l, h; .reg .b128 t; mov.b64 l, {%1, %2}; mov.b64 h, {%3, %4}; mov.b128 t, {l, h}; st.relaxed.gpu.global.b128 [%0], t; }"
        :: "l"(p), "r"(a), "r"(b), "r"(c), "r"(d) : "memory");
}
__device__ __forceinline__ void ld_pkt(const uint4* p, uint32_t* v) {
    asm volatile("{ .reg .b64 l, h; .reg .b128 t; ld.relaxed.gpu.global.b128 t, [%4]; mov.b128 {l, h}, t; mov.b64 {%0, %1}, l; mov.b64 {%2, %3}, h; }"
        : "=r"(v[0]), "=r"(v[1]), "=r"(v[2]), "=r"(v[3]) : "l"(p) : "memory");
}
template <int NP> __device__ __forceinline__ void recv_issue(const uint4* src, uint32_t* raw) {
#pragma unroll
    for (int i = 0; i < NP; i++) ld_pkt(src + i * 256, &raw[i * 4]);
}
__device__ __forceinline__ void send_frag(uint4* dst, const uint32_t* a, uint32_t tagHi) { st_pkt(dst, a[0], a[1], a[2], prmt(a[3], tagHi, 0x7610)); }
__device__ __forceinline__ void send_extra(uint4* dst, const uint32_t* a, uint32_t tagHi) {
    st_pkt(dst, prmt(a[3], a[7], 0x7632), prmt(a[11], a[15], 0x7632), prmt(a[19], a[23], 0x7632), prmt(a[27], tagHi, 0x7632));
}
__device__ __forceinline__ void fix_frags(uint32_t* a) {
#pragma unroll
    for (int i = 0; i < 7; i++) a[4 * i + 3] = prmt(a[4 * i + 3], a[28 + (i >> 1)], (i & 1) ? 0x7610 : 0x5410);
}
__device__ __forceinline__ void stsm4(uint32_t addr, uint32_t a, uint32_t b, uint32_t c, uint32_t d) {
    asm volatile("stmatrix.sync.aligned.m8n8.x4.shared.b16 [%0], {%1, %2, %3, %4};" :: "r"(addr), "r"(a), "r"(b), "r"(c), "r"(d) : "memory");
}
__device__ __forceinline__ void tma_reduce_add(const CUtensorMap* m, uint32_t src, int c0, int c1) {
    asm volatile("cp.reduce.async.bulk.tensor.2d.global.shared::cta.add.bulk_group [%0, {%2, %3}], [%1];"
        :: "l"((uint64_t)m), "r"(src), "r"(c0), "r"(c1) : "memory");
    asm volatile("cp.async.bulk.commit_group;" ::: "memory");
}
template <int NH> __device__ __forceinline__ void epi_frag(const float (&acc)[2 * NH], int fr, uint32_t* h4) {
#pragma unroll
    for (int i = 0; i < 4; i++) {
        int j = fr * 8 + i * 2;
        h4[i] = swiglu2(acc[j], acc[NH + j], acc[j + 1], acc[NH + j + 1]);
    }
}

struct Params {
    uint64_t pad[8];
    CUtensorMap x;
    CUtensorMap wa[2];
    CUtensorMap wc[2];
    CUtensorMap w2l;
    CUtensorMap w2h;
    CUtensorMap w2c;
    CUtensorMap oa;
    CUtensorMap oc;
};

__host__ __device__ constexpr int st_atom(int r) { return r < 6 ? (r & 1) : r < 10 ? 0 : r < 14 ? 1 : 2; }
__host__ __device__ constexpr int st_k(int r) { return r < 6 ? (r >> 1) : r < 10 ? r - 3 : r < 14 ? r - 7 : r - 18; }
__host__ __device__ constexpr int d_slot(int i) {
    return i == 0 ? 11 : i == 1 ? 12 : i == 2 ? 7 : i == 3 ? 13 : i < 7 ? 4 + i : i == 7 ? 11 : i == 8 ? 12 : i == 9 ? 4 : i == 10 ? 6 : i == 11 ? 5 : i - 8;
}
__host__ __device__ constexpr int d_use(int i) {
    return (i == 9 || i == 11) ? 2 : d_slot(i) < 7 ? 1 : (i < 2 || i == 3) ? 3 : 4;
}
__host__ __device__ constexpr int d_issue(int n) {
    return n < 2 ? n : n == 2 ? 3 : n == 3 ? 2 : n == 4 ? 12 : n == 5 ? 4 : n == 6 ? 13 : n < 9 ? n - 2 : n == 9 ? 10 : n == 10 ? 8 : n == 11 ? 7 : n == 12 ? 9 : 11;
}
__host__ __device__ constexpr int d_chunk(int i) { return i < 4 ? (i & 1) : i < 8 ? ((i >> 1) & 1) : 2; }
__host__ __device__ constexpr int d_part(int i) { return i < 4 ? (i >> 1) : i < 8 ? 2 + (i & 1) : i < 12 ? (i & 3) : 0; }

__host__ __device__ constexpr int o_off(int c) { return c < 2 ? 3 * SLOT + c * 4096 : (c - 2) * SLOT; }

__global__ void __cluster_dims__(2, 1, 1) __launch_bounds__(NTHREADS, 1)
swiglu_fused_kernel(const uint8_t* __restrict__ xp, const uint8_t* __restrict__ w1p, const uint8_t* __restrict__ w3p,
                    const uint8_t* __restrict__ w2p, __nv_bfloat16* __restrict__ out, const __grid_constant__ Params prm) {
    extern __shared__ uint8_t smem_raw[];
    uint32_t base = (smem_u32(smem_raw) + 1023) & ~1023u;
    const uint32_t fullb = base + NSLOT * SLOT, emptyb = fullb + 8 * NSLOT;
    const uint32_t tagb = emptyb + 8 * NSLOT, zerob = tagb + 8, tagw = zerob + 8, stgb = tagw + 8;
    const int warp = __shfl_sync(0xffffffff, threadIdx.x >> 5, 0);
    uint32_t rank;
    asm volatile("mov.u32 %0, %%cluster_ctarank;" : "=r"(rank));
    const int cl = blockIdx.x >> 1;
    const uint32_t c = (uint32_t)(cl - 4) & 63u;
    const uint32_t v = c < 60u ? c + ((max(c, 25u) * 37u - 925u) >> 8) : 8u * c - 448u;
    const int f = v >> 3, grp = (v + (f >> 1)) & 7;
    const int mt = grp * 2 + (int)rank;
    const int q = f & 1;

    const int colA = f * BF + q * 96;
    if (warp >= 8) {
        asm volatile("setmaxnreg.dec.sync.aligned.u32 24;");
        if (elect_one()) {
            if (warp == 8) {
                mbar_init(fullb + 8 * 8, 1); mbar_init(fullb + 8 * 9, 1); mbar_init(fullb + 8, 1); mbar_init(fullb + 8 * 7, 1);
                asm volatile("fence.mbarrier_init.release.cluster;" ::: "memory");
#pragma unroll
                for (int r = 1; r < NLOCAL; r++) {
                    mbar_expect_tx(fullb + 8 * (7 + r), SLOT);
                    tma2d(base + (7 + r) * SLOT, &prm.wa[0], colA + st_atom(r) * 64, st_k(r) * 64, fullb + 8 * (7 + r));
                    tma2d(base + (7 + r) * SLOT + 8192, &prm.wa[1], colA + st_atom(r) * 64, st_k(r) * 64, fullb + 8 * (7 + r));
                }
                mbar_expect_tx(fullb + 8, SLOT);
                tma2d(base + SLOT, &prm.x, 64, mt * BM, fullb + 8);
                asm volatile("mbarrier.arrive.shared::cta.b64 _, [%0];" :: "r"(fullb + 8 * 7) : "memory");
            } else if (warp == 9) {
#pragma unroll
                for (int s = 0; s < NSLOT; s++) mbar_init(emptyb + 8 * s, 4);
            } else if (warp == 10) {
                mbar_init(tagb, 1); mbar_init(zerob, 1);
#pragma unroll
                for (int s = 0; s < 10; s++) mbar_init(stgb + 8 * s, 4);
            } else {
#pragma unroll
                for (int s = 2; s < NSLOT; s++) if (s < 7 || s >= 7 + NLOCAL) mbar_init(fullb + 8 * s, 1);
            }
            asm volatile("fence.mbarrier_init.release.cluster;" ::: "memory");
            asm volatile("fence.proxy.async.shared::cta;" ::: "memory");
        }
        __syncwarp();
        asm volatile("barrier.cluster.arrive.relaxed.aligned;" ::: "memory");
        asm volatile("barrier.cluster.wait.acquire.aligned;" ::: "memory");
        if (warp == 8 && elect_one()) {
#pragma unroll
            for (int r = 0; r < 7; r++) {
                const int sl = 7 + r;
                if (r >= NLOCAL) {
                    mbar_expect_tx(fullb + 8 * sl, SLOT);
                    tma2d_mc(base + sl * SLOT + rank * 8192, &prm.wa[rank], colA + st_atom(r) * 64, st_k(r) * 64, fullb + 8 * sl);
                }
                if (r < 6) {
                    if (r == 3 || r == 5) { const int k = (r + 1) / 2; mbar_expect_tx(fullb + 8 * k, SLOT); tma2d(base + k * SLOT, &prm.x, k * 64, mt * BM, fullb + 8 * k); }
                } else {
#pragma unroll
                    for (int k = 4; k < 7; k++) { mbar_expect_tx(fullb + 8 * k, SLOT); tma2d(base + k * SLOT, &prm.x, k * 64, mt * BM, fullb + 8 * k); }
                }
            }
            const CUtensorMap* wa = &prm.wa[rank];
            const CUtensorMap* wc = &prm.wc[rank];
            prefetch_tmap(wc); prefetch_tmap(&prm.w2l); prefetch_tmap(&prm.w2h); prefetch_tmap(&prm.w2c); prefetch_tmap(&prm.oa); prefetch_tmap(&prm.oc);
            const int col = f * BF, colB = col + (q ? 32 : 128), colC = col + (q ? 0 : 192);
            const uint32_t half = rank * 8192;
#pragma unroll
            for (int r = 7; r < 25; r++) {
                const int sl = 7 + r % 7;
                mbar_wait(emptyb + 8 * sl, (r / 7 - 1) & 1);
                mbar_expect_tx(fullb + 8 * sl, SLOT);
                if (r >= 14 && r < 18) tma2d_mc(base + sl * SLOT + half, wc, colC, (r - 14) * 128, fullb + 8 * sl);
                else tma2d_mc(base + sl * SLOT + half, wa, st_atom(r) < 2 ? colA + st_atom(r) * 64 : colB, st_k(r) * 64, fullb + 8 * sl);
            }
#pragma unroll
            for (int n = 0; n < 14; n++) {
                const int i = d_issue(n), sl = d_slot(i);
                mbar_wait(emptyb + 8 * sl, (d_use(i) - 1) & 1);
                const int fo = (d_part(i) & 1) ? (f ^ 1) : f, r0 = fo * BF;
                if (i >= 12) {
                    mbar_expect_tx(fullb + 8 * sl, 224 * 64);
                    tma2d_mc(base + sl * SLOT + rank * 7168, &prm.w2c, 192 + (i - 12) * 32, r0 + (int)rank * 112, fullb + 8 * sl);
                } else if (d_part(i) < 2) {
                    mbar_expect_tx(fullb + 8 * sl, 128 * 128);
                    tma2d_mc(base + sl * SLOT + rank * 8192, &prm.w2l, q * 256 + d_chunk(i) * 64, r0 + (fo & 1) * 96 + (int)rank * 64, fullb + 8 * sl);
                } else {
                    mbar_expect_tx(fullb + 8 * sl, 96 * 128);
                    tma2d_mc(base + sl * SLOT + rank * 6144, &prm.w2h, q * 256 + d_chunk(i) * 64, r0 + ((fo & 1) ? 0 : 128) + (int)rank * 48, fullb + 8 * sl);
                }
            }
        } else if (warp >= 10) {
            const int lane = threadIdx.x & 31, w = warp - 10;
            if (w == 0) {
                mbar_wait(fullb + 8 * 2, 0);
                if (lane < 14)
                    asm volatile("cp.async.bulk.prefetch.L2.global [%0], %1;"
                        :: "l"(((lane & 1) ? w3p : w1p) + (size_t)((lane >> 1) * 64 + (blockIdx.x >> 1)) * (F_FF * 2) + (blockIdx.x & 1) * F_FF), "r"(F_FF) : "memory");
                __syncwarp();
            }
            if (elect_one()) {
                if (w == 0) {
                    mbar_wait(fullb + 8 * 3, 0);
                    asm volatile("cp.async.bulk.prefetch.L2.global [%0], %1;" :: "l"(w2p + (size_t)blockIdx.x * (14 * D_MODEL * 2)), "r"(14 * D_MODEL * 2) : "memory");
                }
                mbar_wait(zerob, 0);
                asm volatile("fence.proxy.async.global;" ::: "memory");
#pragma unroll
                for (int c = 0; c < 5; c++) {
                    mbar_wait(stgb + 8 * (2 * c + w), 0);
                    asm volatile("fence.proxy.async.shared::cta;" ::: "memory");
                    const uint32_t src = base + w * 8192 + o_off(c);
                    if (c >= 2) tma_reduce_add(&prm.oa, src, q * 256 + (c - 2) * 64, mt * BM + w * 64);
                    else tma_reduce_add(&prm.oc, src, 192 + c * 32, mt * BM + w * 64);
                }
                asm volatile("cp.async.bulk.wait_group.read 0;" ::: "memory");
            }
        } else if (warp == 9) {
            const int lane = threadIdx.x & 31;
            uint32_t epoch;
            asm volatile("ld.relaxed.gpu.global.u32 %0, [%1];" : "=r"(epoch) : "l"(g_epoch + blockIdx.x) : "memory");
            uint4* z = reinterpret_cast<uint4*>(out + (size_t)(mt * BM + f * 16) * D_MODEL) + lane;
#pragma unroll 4
            for (int i = 0; i < 28; i++) z[i * 32] = make_uint4(0, 0, 0, 0);
            if (lane == 0) {
                asm volatile("st.shared.u32 [%0], %1;" :: "r"(tagw), "r"((epoch + 1) << 16) : "memory");
                asm volatile("mbarrier.arrive.shared::cta.b64 _, [%0];" :: "r"(tagb) : "memory");
            }
            mbar_wait(fullb + 8 * 6, 0);
            uint4* pw = g_hbox + (size_t)((mt * 8 + f) ^ 1) * (16 * 256) + 13 * 256 + lane;
#pragma unroll 4
            for (int i = 0; i < 24; i++) st_pkt(pw + i * 32, 0, 0, 0, ~((epoch + 1) << 16));
            asm volatile("fence.proxy.async.global;" ::: "memory");
            asm volatile("fence.acq_rel.gpu;" ::: "memory");
            __syncwarp();
            if (lane == 0) {
                uint32_t* cnt = g_zcnt + mt * 32;
                asm volatile("red.release.gpu.global.add.u32 [%0], 1;" :: "l"(cnt) : "memory");
                const uint32_t target = (epoch + 1) * 8;
                uint32_t v, n = 0;
#pragma unroll 1
                do {
                    asm volatile("ld.acquire.gpu.global.u32 %0, [%1];" : "=r"(v) : "l"(cnt) : "memory");
                    if ((int)(v - target) >= 0) break;
                    __nanosleep(200);
                } while (++n < POLL_LIMIT);
                asm volatile("fence.proxy.async.global;" ::: "memory");
                asm volatile("mbarrier.arrive.shared::cta.b64 _, [%0];" :: "r"(zerob) : "memory");
                g_epoch[blockIdx.x] = epoch + 1;
            }
        }
    } else {
        {
            const int row = threadIdx.x >> 3, ch = threadIdx.x & 7;
            const uint32_t so = row * 128 + ((ch ^ (row & 7)) << 4);
            const uint8_t* gx = xp + (uint32_t)((mt * BM + row) * (D_MODEL * 2) + ch * 16);
            const uint32_t go = row * (F_FF * 2) + colA * 2 + ch * 16;
            asm volatile("cp.async.cg.shared.global [%0], [%1], 16;\n cp.async.cg.shared.global [%0+114688], [%2], 16;\n"
                         "cp.async.cg.shared.global [%0+122880], [%3], 16;\n cp.async.cg.shared.global [%0+4096], [%1+28672], 16;\n"
                         "cp.async.cg.shared.global [%0+118784], [%2+114688], 16;\n cp.async.cg.shared.global [%0+126976], [%3+114688], 16;\n"
                         "cp.async.cg.shared.global [%0+8192], [%1+57344], 16;\n cp.async.cg.shared.global [%0+12288], [%1+86016], 16;\n"
                         :: "r"(base + so), "l"(gx), "l"(w1p + go), "l"(w3p + go) : "memory");
        }
        asm volatile("barrier.cluster.arrive.relaxed.aligned;" ::: "memory");
        {
            float junk[64];
            const uint32_t d0 = (base & 0x3FFFF) >> 4;
            wg_fence();
#pragma unroll
            for (int j = 0; j < 2; j++) wgmma_ss_n128(junk, d0, dlo(6 * SLOT, 16), HI128, d0, dlo(13 * SLOT, 8192), HI128, j != 0);
            wg_commit();
            wg_wait<0>();
            pin(junk);
            if (blockIdx.x > 4096) asm volatile("st.shared.f32 [%0], %1;" :: "r"(base), "f"(junk[0]) : "memory");
        }
        asm volatile("setmaxnreg.inc.sync.aligned.u32 240;");
        asm volatile("barrier.cluster.wait.acquire.aligned;" ::: "memory");
        const int wg = warp >> 2;
        const int tid = threadIdx.x;
        const int cta = mt * 8 + f;
        uint32_t rel;
        asm volatile("mapa.shared::cluster.u32 %0, %1, %2;" : "=r"(rel) : "r"(emptyb), "r"((uint32_t)(tid & 1)));
        const bool signaller = (tid & 127) < 2;
        auto release = [&](int sl) { if (signaller) mbar_arrive_cluster(rel + 8 * sl); };
        const uint32_t db = (base & 0x3FFFF) >> 4;
        const uint32_t da = db + wg * 512;

        uint32_t ho[56];
        uint32_t hl[32], hh[32];
        float accA0[64], accA1[64], accB[64], accC[32];
        uint32_t tagHi = 0;
        uint4* hdst = g_hbox + (size_t)(cta ^ 1) * (16 * 256) + tid;
        const uint4* hsrc = g_hbox + (size_t)cta * (16 * 256) + tid;
        auto frag_out = [&](int i) { send_frag(hdst + (i < 7 ? i : i + 1) * 256, &ho[4 * i], tagHi); };
        auto stage = [&](int r, float (&acc)[64]) {
            const int sl = 7 + r % 7, k = st_k(r);
            wg_fence();
#pragma unroll
            for (int j = 0; j < 4; j++)
                wgmma_ss_n128(acc, da, dlo(k * SLOT + j * 32, 16), HI128, db, dlo(sl * SLOT + j * 2048, 8192), HI128, (k | j) != 0);
            wg_commit();
        };
        auto wait_st = [&](int r) {
            if (r < 14 && st_atom(r) == 0) mbar_wait(fullb + 8 * st_k(r), 0);
            mbar_wait(fullb + 8 * (7 + r % 7), (r / 7) & 1);
        };
        auto wait_d = [&](int i) { mbar_wait(fullb + 8 * d_slot(i), d_use(i) & 1); };
        wg_fence(); wg_commit(); wg_wait<0>();
        asm volatile("cp.async.wait_all;" ::: "memory");
        asm volatile("fence.proxy.async.shared::cta;" ::: "memory");
        asm volatile("bar.sync 2, 256;" ::: "memory");
#pragma unroll
        for (int r = 0; r < 25; r++) {
            if (r >= 14 && r < 18) {
                const int sl = 7 + r % 7, s = r - 14;
                wg_fence();
#pragma unroll
                for (int j = 0; j < (s < 3 ? 8 : 4); j++)
                    wgmma_ss_n64(accC, da, dlo((2 * s + (j >> 2)) * SLOT + (j & 3) * 32, 16), HI128,
                                 db, dlo(sl * SLOT + j * 1024, 8192), HI64, (s | j) != 0);
                wg_commit();
            } else if (st_atom(r) == 0) stage(r, accA0); else if (st_atom(r) == 1) stage(r, accA1); else stage(r, accB);
            if (r == 7) {
                mbar_wait(tagb, 0);
                asm volatile("ld.shared.u32 %0, [%1];" : "=r"(tagHi) : "r"(tagw) : "memory");
            }
            if (r >= 11 && r <= 14) epi_frag<32>(accA0, r - 11, &ho[4 * (r - 11)]);
            if (r >= 18 && r <= 21) epi_frag<32>(accA1, r - 18, &ho[4 * (r - 14)]);
            if (r == 22 || r == 23) epi_frag<16>(accC, r - 22, &ho[4 * (r - 14)]);
            if (r == 22) { frag_out(8); recv_issue<4>(hsrc, hl); }
            if (r == 24) recv_issue<4>(hsrc + 4 * 256, &hl[16]);
            if (r < 24) wait_st(r + 1); else { wait_d(0); wait_d(1); }
            if (r == 23) mbar_wait(zerob, 0);
            if (r >= 11 && r <= 14) frag_out(r - 11);
            if (r >= 18 && r <= 23 && r != 22) frag_out(r - 14);
            if (r > 0) { wg_wait<1>(); release(7 + (r - 1) % 7); }
            if (r == 20) send_extra(hdst + 7 * 256, &ho[0], tagHi);
            if (r == 23 || r == 24) release(r - 19);
            if (r == 10) pin(accA0);
            if (r == 14) pin(accA1);
            if (r == 18) pin(accC);
        }
        float accXY[64], accX[32], accY[32], accZ[16], accW[16];
        auto hi_base = [&](int part, int j) {
            const uint32_t even = (part & 1) ? q : (q ^ 1);
            return j < 2 ? db + even * (64 * 128 >> 4) : db - even * (32 * 128 >> 4);
        };
        auto mma128 = [&](int i, const uint32_t* a, int j0, int j1, bool first) {
            const int part = d_part(i);
            wg_fence();
#pragma unroll
            for (int j = j0; j < j1; j++)
                wgmma_rs_n128(accXY, a[4 * j], a[4 * j + 1], a[4 * j + 2], a[4 * j + 3], part >= 2 ? hi_base(part, j) : db,
                              dlo(d_slot(i) * SLOT + j * 2048, (d_slot(i + 1) - d_slot(i)) * SLOT), HI128, !(first && j == 0));
            wg_commit();
        };
        auto group = [&](int i, float (&acc)[32], const uint32_t* a, bool first, int il = 0, int j0 = 0, int j1 = 8) {
            const int sl = d_slot(i), part = d_part(i);
            wg_fence();
            if (part == 3) {
                if (j0 == 0) wgmma_rs_n64(acc, a[0], a[1], a[2], a[3], db, dlo(d_slot(il) * SLOT + 7 * 2048, 8192), HI128, true);
                a += 4;
            }
#pragma unroll
            for (int j = j0; j < j1 && j < (part == 0 ? 8 : part == 1 ? 7 : 6); j++)
                wgmma_rs_n64(acc, a[4 * j], a[4 * j + 1], a[4 * j + 2], a[4 * j + 3],
                             part >= 2 ? hi_base(part, j) : db, dlo(sl * SLOT + j * 2048, 8192), HI128, !(first && j == 0));
            wg_commit();
        };
        auto group32 = [&](int i, float (&acc)[16], int j0 = 0, int j1 = 14) {
            const int sl = d_slot(i);
            const uint32_t bA = db + q * (96 * 64 >> 4), bC = db + (64 * 64 >> 4) - q * (192 * 64 >> 4), bB = db - (32 * 64 >> 4) - q * (96 * 64 >> 4);
            wg_fence();
#pragma unroll
            for (int j = j0; j < j1; j++)
                wgmma_rs_n32(acc, ho[4 * j], ho[4 * j + 1], ho[4 * j + 2], ho[4 * j + 3], j < 8 ? bA : j < 10 ? bC : bB,
                             dlo(sl * SLOT + j * 1024, 8192), HI64, j != 0);
            wg_commit();
        };
        const int lane = tid & 31;
        const int srow = ((tid >> 5) & 3) * 16 + (lane & 15);
        const uint32_t stg = base + wg * 8192;
        auto flush = [&](int c) {
            __syncwarp();
            if (lane == 0) asm volatile("mbarrier.arrive.shared::cta.b64 _, [%0];" :: "r"(stgb + 8 * (2 * c + wg)) : "memory");
        };
        auto put64 = [&](int c, float (&acc)[32]) {
#pragma unroll
            for (int b = 0; b < 8; b += 2)
                stsm4(stg + o_off(c) + srow * 128 + (((b + (lane >> 4)) ^ (srow & 7)) << 4),
                      pack_bf16(acc[4 * b], acc[4 * b + 1]), pack_bf16(acc[4 * b + 2], acc[4 * b + 3]),
                      pack_bf16(acc[4 * b + 4], acc[4 * b + 5]), pack_bf16(acc[4 * b + 6], acc[4 * b + 7]));
            flush(c);
        };
        auto put32 = [&](int c, float (&acc)[16]) {
            uint32_t pk[8];
#pragma unroll
            for (int j = 0; j < 8; j++) pk[j] = pack_bf16(acc[2 * j], acc[2 * j + 1]);
#pragma unroll
            for (int b = 0; b < 4; b += 2)
                stsm4(stg + o_off(c) + srow * 64 + (((b + (lane >> 4)) ^ ((srow >> 1) & 3)) << 4), pk[2 * b], pk[2 * b + 1], pk[2 * b + 2], pk[2 * b + 3]);
            flush(c);
        };

        mma128(0, &ho[0], 0, 3, true);
        wg_wait<1>();
        release(10); release(6);
        pin(accB);
        mma128(0, &ho[0], 3, 5, false);
        epi_frag<32>(accB, 0, &ho[40]); frag_out(10);
        wg_wait<1>();
        mma128(0, &ho[0], 5, 8, false);
        epi_frag<32>(accB, 1, &ho[44]); frag_out(11);
        wait_d(2); wait_d(3);
        recv_check8(hsrc, hl, tagHi);
        fix_frags(hl);
        wg_wait<1>();
        mma128(2, hl, 0, 4, false);
        epi_frag<32>(accB, 2, &ho[48]); frag_out(12);
        wg_wait<1>();
        release(d_slot(0)); release(d_slot(1));
        mma128(2, hl, 4, 7, false);
        epi_frag<32>(accB, 3, &ho[52]); frag_out(13);
        wait_d(12);
        wg_wait<1>();
        send_extra(hdst + 15 * 256, &ho[28], tagHi);
        group32(12, accZ);
        recv_issue<5>(hsrc + 8 * 256, hh);
        wait_d(13);
        wg_wait<1>();
        pin(accXY);
#pragma unroll
        for (int i = 0; i < 32; i++) {
            asm volatile("mov.b32 %0, %1;" : "=f"(accX[i]) : "f"(accXY[i]));
            asm volatile("mov.b32 %0, %1;" : "=f"(accY[i]) : "f"(accXY[32 + i]));
        }
        group32(13, accW, 0, K32);
        wg_wait<1>();
        release(d_slot(12));
        pin(accZ);
        put32(0, accZ);
        group32(13, accW, K32, K32 + 3);
        wait_d(4);
        recv_issue<3>(hsrc + 13 * 256, &hh[20]);
        group32(13, accW, K32 + 3, 14);
        group(4, accX, &ho[32], false, 0, 0, K64);
        wg_wait<1>();
        release(d_slot(13));
        pin(accW);
        put32(1, accW);
        group(4, accX, &ho[32], false, 0, K64, 8);
        wait_d(6);
        group(6, accY, &ho[32], false);
        wait_d(5); wait_d(7);
        recv_check5(hsrc + 8 * 256, hh, tagHi);
        if (recv_check3(hsrc + 13 * 256, &hh[20], tagHi) > POLL_LIMIT + 1) {
#pragma unroll
            for (int i = 0; i < 16; i++) asm volatile("st.shared.f32 [%0], %1;" :: "r"(stg + i * 4), "f"(accW[i]) : "memory");
        }
        fix_frags(hh);
        group(5, accX, hh, false, 2);
        group(7, accY, hh, false, 3, 0, K64 - 1);
        wg_wait<1>();
        pin(accX);
        put64(2, accX);
        group(7, accY, hh, false, 3, K64 - 1, 8);
        wait_d(8); wait_d(10); wait_d(9); wait_d(11);
        group(8, accX, &ho[0], true, 0, 0, KS);
        wg_wait<1>();
        pin(accY);
        put64(3, accY);
        if (wg == 1) asm volatile("bar.sync 1, 256;" ::: "memory");
        group(8, accX, &ho[0], false, 0, KS, 8);
        group(10, accX, &ho[32], false);
        group(9, accX, hl, false);
        group(11, accX, hh, false, 9);
        if (wg == 0) asm volatile("bar.arrive 1, 256;" ::: "memory");
        wg_wait<0>();
        pin(accX);
        put64(4, accX);
    }
}

__global__ void fallback_h(const __nv_bfloat16* __restrict__ x, const __nv_bfloat16* __restrict__ w1, const __nv_bfloat16* __restrict__ w3) {
    const int c = blockIdx.x * 256 + threadIdx.x, m = blockIdx.y;
    float g = 0.f, u = 0.f;
    for (int k = 0; k < D_MODEL; k++) {
        const float xv = __bfloat162float(x[m * D_MODEL + k]);
        g += xv * __bfloat162float(w1[k * F_FF + c]);
        u += xv * __bfloat162float(w3[k * F_FF + c]);
    }
    reinterpret_cast<__nv_bfloat16*>(g_hbox)[(size_t)m * F_FF + c] = __float2bfloat16(swiglu(g, u));
}
__global__ void fallback_out(const __nv_bfloat16* __restrict__ w2, __nv_bfloat16* __restrict__ out) {
    const int d = threadIdx.x, m = blockIdx.x;
    const __nv_bfloat16* h = reinterpret_cast<const __nv_bfloat16*>(g_hbox) + (size_t)m * F_FF;
    float a = 0.f;
    for (int k = 0; k < F_FF; k++) a += __bfloat162float(h[k]) * __bfloat162float(w2[k * D_MODEL + d]);
    out[m * D_MODEL + d] = __float2bfloat16(a);
}

typedef CUresult (*PFN_encodeTiled)(CUtensorMap*, CUtensorMapDataType, cuuint32_t, void*, const cuuint64_t*, const cuuint64_t*,
                                    const cuuint32_t*, const cuuint32_t*, CUtensorMapInterleave, CUtensorMapSwizzle,
                                    CUtensorMapL2promotion, CUtensorMapFloatOOBfill);

static void make_map(PFN_encodeTiled enc, CUtensorMap* m, const void* ptr, uint64_t inner, uint64_t outer, uint32_t bi, uint32_t bo,
                     CUtensorMapSwizzle sw) {
    cuuint64_t gd[2] = {inner, outer};
    cuuint64_t gs[1] = {inner * 2};
    cuuint32_t bd[2] = {bi, bo};
    cuuint32_t es[2] = {1, 1};
    enc(m, CU_TENSOR_MAP_DATA_TYPE_BFLOAT16, 2, const_cast<void*>(ptr), gd, gs, bd, es, CU_TENSOR_MAP_INTERLEAVE_NONE, sw,
        CU_TENSOR_MAP_L2_PROMOTION_L2_128B, CU_TENSOR_MAP_FLOAT_OOB_FILL_NONE);
}

extern "C" void kernel_launch(void* const* d_in, const int* in_sizes, int n_in, void* d_out, int out_size) {
    cudaLaunchConfig_t cfg = {};
    cfg.gridDim = dim3(128);
    cfg.blockDim = dim3(NTHREADS);
    cfg.dynamicSmemBytes = SMEM_BYTES;
    cfg.stream = cudaStreamPerThread;

    static PFN_encodeTiled enc = nullptr;
    static bool fused = false;
    static bool init = false;
    if (!init) {
        init = true;
        void* fn = nullptr;
        cudaDriverEntryPointQueryResult qr;
        cudaGetDriverEntryPoint("cuTensorMapEncodeTiled", &fn, cudaEnableDefault, &qr);
        enc = (PFN_encodeTiled)fn;
        cudaFuncSetAttribute(swiglu_fused_kernel, cudaFuncAttributeMaxDynamicSharedMemorySize, SMEM_BYTES);
        cudaLaunchAttribute at;
        at.id = cudaLaunchAttributeClusterDimension;
        at.val.clusterDim.x = 2; at.val.clusterDim.y = 1; at.val.clusterDim.z = 1;
        cudaLaunchConfig_t qc = cfg;
        qc.attrs = &at; qc.numAttrs = 1;
        int ncl = 0;
        fused = enc && cudaOccupancyMaxActiveClusters(&ncl, swiglu_fused_kernel, &qc) == cudaSuccess && ncl >= 64;
        (void)cudaGetLastError();
    }
    if (!fused) {
        fallback_h<<<dim3(F_FF / 256, M_TOK), 256, 0, cudaStreamPerThread>>>((const __nv_bfloat16*)d_in[0], (const __nv_bfloat16*)d_in[1], (const __nv_bfloat16*)d_in[2]);
        fallback_out<<<M_TOK, D_MODEL, 0, cudaStreamPerThread>>>((const __nv_bfloat16*)d_in[3], (__nv_bfloat16*)d_out);
        return;
    }
    Params prm = {};
    make_map(enc, &prm.x, d_in[0], D_MODEL, M_TOK, 64, 128, CU_TENSOR_MAP_SWIZZLE_128B);
    make_map(enc, &prm.wa[0], d_in[1], F_FF, D_MODEL, 64, 64, CU_TENSOR_MAP_SWIZZLE_128B);
    make_map(enc, &prm.wa[1], d_in[2], F_FF, D_MODEL, 64, 64, CU_TENSOR_MAP_SWIZZLE_128B);
    make_map(enc, &prm.wc[0], d_in[1], F_FF, D_MODEL, 32, 128, CU_TENSOR_MAP_SWIZZLE_64B);
    make_map(enc, &prm.wc[1], d_in[2], F_FF, D_MODEL, 32, 128, CU_TENSOR_MAP_SWIZZLE_64B);
    make_map(enc, &prm.w2l, d_in[3], D_MODEL, F_FF, 64, 64, CU_TENSOR_MAP_SWIZZLE_128B);
    make_map(enc, &prm.w2h, d_in[3], D_MODEL, F_FF, 64, 48, CU_TENSOR_MAP_SWIZZLE_128B);
    make_map(enc, &prm.w2c, d_in[3], D_MODEL, F_FF, 32, 112, CU_TENSOR_MAP_SWIZZLE_64B);
    make_map(enc, &prm.oa, d_out, D_MODEL, M_TOK, 64, 64, CU_TENSOR_MAP_SWIZZLE_128B);
    make_map(enc, &prm.oc, d_out, D_MODEL, M_TOK, 32, 64, CU_TENSOR_MAP_SWIZZLE_64B);
    cudaLaunchKernelEx(&cfg, swiglu_fused_kernel, (const uint8_t*)d_in[0], (const uint8_t*)d_in[1], (const uint8_t*)d_in[2],
                       (const uint8_t*)d_in[3], (__nv_bfloat16*)d_out, prm);
}
```
